```python
import torch

def _softmax(x, axis=-1):
    return torch.softmax(x, dim=axis)
def _gelu(x):
    return torch.nn.functional.gelu(x, approximate="tanh")
def _silu(x):
    return torch.nn.functional.silu(x)
def _sigmoid(x):
    return torch.sigmoid(x)
def _layernorm(x, axis=-1, eps=1e-5):
    m = x.mean(dim=axis, keepdim=True)
    v = x.var(dim=axis, keepdim=True, unbiased=False)
    return (x - m) / torch.sqrt(v + eps)
def _scatter_add(tgt, idx, src, axis=0):
    return tgt.clone().index_add_(axis, idx, src)
def _segment_sum(src, seg, n):
    out = torch.zeros((n,) + src.shape[1:], dtype=src.dtype)
    return out.index_add_(0, seg, src)
def _pad(x, pw):
    flat = tuple(v for pair in reversed(pw) for v in pair)
    return torch.nn.functional.pad(x, flat)

kernel_name = 'interleave_layers__spectral_fnet__swiglu_ffn__prompt'

def setup_inputs():

    _w = (lambda a: (lambda t: t.to(torch.bfloat16) if t.is_floating_point() else t)(torch.as_tensor(a)))
    def _A_setup():
        B, S, D = 1, 2048, 640
        ns = torch.arange(S)[:, None] * torch.arange(S)[None, :]
        nd = torch.arange(D)[:, None] * torch.arange(D)[None, :]
        Ws_re = torch.cos(-2.0 * torch.pi * ns / S).to(float)
        Ws_im = torch.sin(-2.0 * torch.pi * ns / S).to(float)
        Wd_re = torch.cos(-2.0 * torch.pi * nd / D).to(float)
        Wd_im = torch.sin(-2.0 * torch.pi * nd / D).to(float)
        return {
            "x": _w((lambda *s: torch.randn(*s, dtype=torch.bfloat16) * 0.05)(B, S, D)),
            "dft_seq_re": _w(Ws_re),
            "dft_seq_im": _w(Ws_im),
            "dft_hid_re": _w(Wd_re),
            "dft_hid_im": _w(Wd_im),
        }
    _A_in = _A_setup()

    def _B_setup():
        B, S, D, F = 1, 2048, 640, 1728
        return {
            "x": _w((lambda *s: torch.randn(*s, dtype=torch.bfloat16) * 0.05)(B, S, D)),
            "w_gate": _w((lambda *s: torch.randn(*s, dtype=torch.bfloat16) * 0.4)(D, F)),
            "w_up": _w((lambda *s: torch.randn(*s, dtype=torch.bfloat16) * 0.4)(D, F)),
            "w_down": _w((lambda *s: torch.randn(*s, dtype=torch.bfloat16) * 0.4)(F, D)),
        }
    _B_in = _B_setup()

    return {
        "A_x": _A_in["x"],
        "A_dft_seq_re": _A_in["dft_seq_re"],
        "A_dft_seq_im": _A_in["dft_seq_im"],
        "A_dft_hid_re": _A_in["dft_hid_re"],
        "A_dft_hid_im": _A_in["dft_hid_im"],
        "B_x": _B_in["x"],
        "B_w_gate": _B_in["w_gate"],
        "B_w_up": _B_in["w_up"],
        "B_w_down": _B_in["w_down"],
    }

def reference(A_x, A_dft_seq_re, A_dft_seq_im, A_dft_hid_re, A_dft_hid_im, B_x, B_w_gate, B_w_up, B_w_down):
    def _A_ref(x, dft_seq_re, dft_seq_im, dft_hid_re, dft_hid_im):
        a = torch.einsum("bsd,ed->bse", x, dft_hid_re)
        b = torch.einsum("bsd,ed->bse", x, dft_hid_im)
        y = torch.einsum("ts,bse->bte", dft_seq_re, a) - torch.einsum("ts,bse->bte", dft_seq_im, b)
        return y

    def _B_ref(x, w_gate, w_up, w_down):
        g = _silu(x @ w_gate)
        u = x @ w_up
        return (g * u) @ w_down

    x = A_x
    x = x + _A_ref(_layernorm(x, axis=-1), A_dft_seq_re, A_dft_seq_im, A_dft_hid_re, A_dft_hid_im)
    x = x + _B_ref(_layernorm(x, axis=-1), B_w_gate, B_w_up, B_w_down)
    x = x + _A_ref(_layernorm(x, axis=-1), A_dft_seq_re, A_dft_seq_im, A_dft_hid_re, A_dft_hid_im)
    x = x + _B_ref(_layernorm(x, axis=-1), B_w_gate, B_w_up, B_w_down)
    return x
```

```cpp
#include <cuda_runtime.h>
#include <cuda_bf16.h>
#include <cuda.h>
#include <stdint.h>
#include <stddef.h>

namespace {

constexpr int S_ = 2048, D_ = 640, F_ = 1728;
constexpr int NCTA = 128, NHELP = 4, NTHREADS = 384;
constexpr uint32_t RING = 222 * 1024;
constexpr int NB = 32;
constexpr float LN_EPS = 1e-5f;
constexpr unsigned SPIN_LIMIT = 1u << 22;
constexpr int TAIL_G1 = 2, TAIL_GU = 2, TAIL_GU1 = 2, TAIL_TM = 4, TAIL_DN = 4;
constexpr unsigned POLL_GAP = 200;
#define KORD(k) ((k) < 16 ? 2 * (k) : 2 * (k) - 31)
constexpr int NP0 = 256, NP1 = 176;
constexpr int NA = 48, NBC = 40, F1 = NP0 / 2 * 8 + 8 * NA;
constexpr int F0 = NP0 / 2 * 8;

__device__ __align__(1024) __nv_bfloat16 g_abT[2][2 * D_ * S_];
__device__ __align__(1024) __nv_bfloat16 g_x1[2 * S_ * D_];
__device__ __align__(1024) __nv_bfloat16 g_x2[S_ * D_];
__device__ __align__(1024) __nv_bfloat16 g_act[S_ * F_];
__device__ __align__(1024) __nv_bfloat16 g_wguT[2 * F_ * D_];
__device__ __align__(1024) __nv_bfloat16 g_wdT[D_ * F_];
__device__ __align__(16) float g_cs[2 * F_];
__device__ __align__(128) uint2 g_csh[2 * D_];
__device__ __align__(128) unsigned g_flagAB[8][32];
__device__ __align__(128) unsigned g_flagG[5][16][32];
__device__ __align__(128) uint4 g_stat[4][8][S_];
__device__ unsigned g_cnt[4 * 32];
__device__ unsigned g_epoch;

constexpr int CNT_W = 0;

constexpr int LSTAGE = 86, NSTAGE = 2 * LSTAGE + 1;
constexpr int O_TM = 12, O_GU = 46;
struct Sched { uint32_t off[NSTAGE]; uint32_t waitW[NSTAGE]; uint32_t waitX[NSTAGE]; };
struct SchedBuilder {
    Sched t{}; int owner[RING / 1024] = {}; int mask[NSTAGE] = {}; int head = 0, c = 0;
    int doneW[4] = {-1, -1, -1, -1}, doneX[4] = {-1, -1, -1, -1};
    constexpr void require(int w, int (&need)[4]) {
        for (int a = 0; a < 4; a++) if (((mask[w] >> a) & 1) && w > need[a]) need[a] = w;
    }
    constexpr int alloc(int kb, int (&need)[4]) {
        if (head + kb > (int)(RING / 1024)) head = 0;
        int o = head;
        for (int i = 0; i < kb; i++) {
            int w = owner[o + i] - 1;
            if (w >= 0 && w != c) require(w, need);
            owner[o + i] = c + 1;
        }
        head += kb;
        return o;
    }
    constexpr uint32_t enc(int (&need)[4], int (&done)[4]) {
        uint32_t r = 0;
        for (int n = 0; n < 4; n++) {
            int best = -1;
            for (int a = 0; a < 4; a++) if (need[a] > done[a] && need[a] > best) best = need[a];
            if (best < 0) break;
            if (n >= 3) throw 1;
            if (c - best > NB / 2) throw 1;
            r |= (uint32_t)(c - best) << (8 * n);
            for (int a = 0; a < 4; a++) if (((mask[best] >> a) & 1) && best > done[a]) done[a] = best;
        }
        return r;
    }
    constexpr void stage(int w, int x, int m, int kind = 0) {
        int nW[4] = {-1, -1, -1, -1}, nX[4] = {-1, -1, -1, -1};
        mask[c] = m;
        int o0 = alloc(w, nW), o1 = kind ? alloc(x, nW) : alloc(x, nX);
        if (kind) for (int a = 0; a < 4; a++) nX[a] = nW[a];
        t.off[c] = o0 | (o1 << 16);
        t.waitW[c] = enc(nW, doneW);
        if (kind != 1) t.waitX[c] = enc(nX, doneX);
        c++;
    }
    constexpr SchedBuilder() {
        for (int L = 0; L < 2; L++) {
            for (int k = 0; k < 10; k++) stage(20, 16, 3);
            stage(20, 0, 4, 1);
            stage(20, 0, 8, 1);
            for (int k = 0; k < 32; k++) stage(16, 20, 3);
            stage(20, 0, 4, 2);
            stage(20, 0, 8, 2);
            for (int k = 0; k < 10; k++) stage(NP0 / 8, 16, 3);
            stage(NP0 / 16, 0, 4, 1);
            stage(NP0 / 16, 0, 8, 1);
            for (int k = 0; k < 10; k++) stage(NP1 / 8, 16, 3);
            stage(NP1 / 16, 0, 4, 1);
            stage(NP1 / 16, 0, 8, 1);
            for (int k = 0; k < 14; k++) stage(20, 16, 3);
            stage(20, 0, 4, 2);
            stage(20, 0, 8, 2);
        }
        if (c != 2 * LSTAGE) throw 1;
    }
};
__constant__ Sched c_sched = SchedBuilder().t;

struct Maps {
    CUtensorMap C[2];
    CUtensorMap AB[2];
    CUtensorMap ABl[2];
    CUtensorMap Wh[2];
    CUtensorMap Xl[2];
    CUtensorMap X1l;
    CUtensorMap X1s;
    CUtensorMap Xo[2];
    CUtensorMap X0r;
    CUtensorMap Wgu[2];
    CUtensorMap Al;
    CUtensorMap As[3];
    CUtensorMap Wd;
    CUtensorMap Rs[3];
    CUtensorMap Rgu;
    CUtensorMap Rd;
    uint8_t role[72];
};

struct Ctl {
    uint64_t full[NB], empty[NB];
    uint64_t stg[4], xch[2], sta[2], abq;
    uint64_t full2[8];
    float2 rowstat[128];
    float cs[432];
    float csh[160];
};

__device__ __forceinline__ uint32_t smem_u32(const void* p) { return (uint32_t)__cvta_generic_to_shared(p); }
__device__ __forceinline__ void mbar_init(uint32_t bar, uint32_t cnt) { asm volatile("mbarrier.init.shared::cta.b64 [%0], %1;" ::"r"(bar), "r"(cnt)); }
__device__ __forceinline__ void mbar_expect_tx(uint32_t bar, uint32_t bytes) { asm volatile("mbarrier.arrive.expect_tx.shared::cta.b64 _, [%0], %1;" ::"r"(bar), "r"(bytes) : "memory"); }
__device__ __forceinline__ void mbar_arrive(uint32_t bar) { asm volatile("mbarrier.arrive.shared::cta.b64 _, [%0];" ::"r"(bar) : "memory"); }
__device__ __forceinline__ bool mbar_try(uint32_t bar, uint32_t parity) {
    uint32_t ok;
    asm volatile("{\n.reg .pred p;\nmbarrier.try_wait.parity.shared::cta.b64 p, [%1], %2;\nselp.u32 %0, 1, 0, p;\n}" : "=r"(ok) : "r"(bar), "r"(parity) : "memory");
    return ok != 0;
}
__device__ __forceinline__ bool mbar_test(uint32_t bar, uint32_t parity) {
    uint32_t ok;
    asm volatile("{\n.reg .pred p;\nmbarrier.test_wait.parity.shared::cta.b64 p, [%1], %2;\nselp.u32 %0, 1, 0, p;\n}" : "=r"(ok) : "r"(bar), "r"(parity) : "memory");
    return ok != 0;
}
__device__ __forceinline__ void mbar_wait(uint32_t bar, uint32_t parity) {
    if (mbar_try(bar, parity)) return;
    unsigned n = 0;
    while (!mbar_try(bar, parity)) { if (++n > SPIN_LIMIT) __trap(); }
}
__device__ __forceinline__ void mbar_wait_cluster(uint32_t bar, uint32_t parity) {
    unsigned n = 0;
    while (true) {
        uint32_t ok;
        asm volatile("{\n.reg .pred p;\nmbarrier.try_wait.parity.acquire.cluster.shared::cta.b64 p, [%1], %2;\nselp.u32 %0, 1, 0, p;\n}" : "=r"(ok) : "r"(bar), "r"(parity) : "memory");
        if (ok) break;
        if (++n > SPIN_LIMIT) __trap();
    }
}
__device__ __forceinline__ uint32_t mapa(uint32_t addr, uint32_t cta) {
    uint32_t r; asm("mapa.shared::cluster.u32 %0, %1, %2;" : "=r"(r) : "r"(addr), "r"(cta)); return r;
}
__device__ __forceinline__ void mbar_arrive_cluster(uint32_t bar, uint32_t cta) {
    asm volatile("mbarrier.arrive.shared::cluster.b64 _, [%0];" ::"r"(mapa(bar, cta)) : "memory");
}
__device__ __forceinline__ void st_async4(uint32_t raddr, uint32_t rbar, uint32_t a, uint32_t b, uint32_t c, uint32_t d) {
    asm volatile("st.async.weak.shared::cluster.mbarrier::complete_tx::bytes.v4.b32 [%0], {%2,%3,%4,%5}, [%1];"
                 ::"r"(raddr), "r"(rbar), "r"(a), "r"(b), "r"(c), "r"(d) : "memory");
}
__device__ __forceinline__ void tma_load(uint32_t dst, const CUtensorMap* m, int c0, int c1, uint32_t bar) {
    asm volatile("cp.async.bulk.tensor.2d.shared::cluster.global.mbarrier::complete_tx::bytes [%0], [%1, {%3, %4}], [%2];"
                 ::"r"(dst), "l"(m), "r"(bar), "r"(c0), "r"(c1) : "memory");
}
__device__ __forceinline__ void tma_load_stream(uint32_t dst, const CUtensorMap* m, int c0, int c1, uint32_t bar, uint64_t pol) {
    asm volatile("cp.async.bulk.tensor.2d.shared::cluster.global.mbarrier::complete_tx::bytes.L2::cache_hint [%0], [%1, {%3, %4}], [%2], %5;"
                 ::"r"(dst), "l"(m), "r"(bar), "r"(c0), "r"(c1), "l"(pol) : "memory");
}
__device__ __forceinline__ void tma_load_mc(uint32_t dst, const CUtensorMap* m, int c0, int c1, uint32_t bar) {
    asm volatile("cp.async.bulk.tensor.2d.shared::cluster.global.mbarrier::complete_tx::bytes.multicast::cluster [%0], [%1, {%3, %4}], [%2], %5;"
                 ::"r"(dst), "l"(m), "r"(bar), "r"(c0), "r"(c1), "h"((uint16_t)3) : "memory");
}
__device__ __forceinline__ void tma_store(const CUtensorMap* m, int c0, int c1, uint32_t src) {
    asm volatile("cp.async.bulk.tensor.2d.global.shared::cta.bulk_group [%0, {%2, %3}], [%1];" ::"l"(m), "r"(src), "r"(c0), "r"(c1) : "memory");
}
__device__ __forceinline__ void l2_prefetch(const void* p, uint32_t bytes) {
    asm volatile("cp.async.bulk.prefetch.L2.global [%0], %1;" ::"l"(p), "r"(bytes) : "memory");
}
__device__ __forceinline__ void bulk_commit_wait_read() {
    asm volatile("cp.async.bulk.commit_group;\ncp.async.bulk.wait_group.read 0;" ::: "memory");
}
__device__ __forceinline__ void bulk_wait() { asm volatile("cp.async.bulk.wait_group 0;" ::: "memory"); }
__device__ __forceinline__ void fence_async_smem() { asm volatile("fence.proxy.async.shared::cta;" ::: "memory"); }
__device__ __forceinline__ void fence_async_all() { asm volatile("fence.proxy.async.global;" ::: "memory"); }
__device__ __forceinline__ void bar_sync(int id, int n) { asm volatile("bar.sync %0, %1;" ::"r"(id), "r"(n) : "memory"); }
__device__ __forceinline__ void bar_arrive(int id, int n) { asm volatile("bar.arrive %0, %1;" ::"r"(id), "r"(n) : "memory"); }
__device__ __forceinline__ void flag_add_release(int idx, unsigned v) { asm volatile("red.release.gpu.global.add.u32 [%0], %1;" ::"l"(&g_cnt[idx * 32]), "r"(v) : "memory"); }
__device__ __forceinline__ void flag_wait(int idx, unsigned target) {
    unsigned v, n = 0;
    while (true) {
        asm volatile("ld.acquire.gpu.global.u32 %0, [%1];" : "=r"(v) : "l"(&g_cnt[idx * 32]) : "memory");
        if ((int)(v - target) >= 0) break;
        if (++n > SPIN_LIMIT) __trap();
    }
    fence_async_all();
}
__device__ __forceinline__ void wg_fence() { asm volatile("wgmma.fence.sync.aligned;" ::: "memory"); }
__device__ __forceinline__ void wg_commit() { asm volatile("wgmma.commit_group.sync.aligned;" ::: "memory"); }
template <int N> __device__ __forceinline__ void wg_wait() { asm volatile("wgmma.wait_group.sync.aligned %0;" ::"n"(N) : "memory"); }
__device__ __forceinline__ uint32_t pack_bf16(float lo, float hi) {
    uint32_t r; asm("cvt.rn.bf16x2.f32 %0, %1, %2;" : "=r"(r) : "f"(hi), "f"(lo)); return r;
}
__device__ __forceinline__ float bf_lo(uint32_t v) { return __uint_as_float(v << 16); }
__device__ __forceinline__ float bf_hi(uint32_t v) { return __uint_as_float(v & 0xFFFF0000u); }
__device__ __forceinline__ void stsm4(uint32_t addr, uint32_t a, uint32_t b, uint32_t c, uint32_t d) {
    asm volatile("stmatrix.sync.aligned.m8n8.x4.shared.b16 [%0], {%1,%2,%3,%4};" ::"r"(addr), "r"(a), "r"(b), "r"(c), "r"(d));
}
__device__ __forceinline__ void stsm2(uint32_t addr, uint32_t a, uint32_t b) {
    asm volatile("stmatrix.sync.aligned.m8n8.x2.shared.b16 [%0], {%1,%2};" ::"r"(addr), "r"(a), "r"(b));
}
__device__ __forceinline__ void stsm4t(uint32_t addr, uint32_t a, uint32_t b, uint32_t c, uint32_t d) {
    asm volatile("stmatrix.sync.aligned.m8n8.x4.trans.shared.b16 [%0], {%1,%2,%3,%4};" ::"r"(addr), "r"(a), "r"(b), "r"(c), "r"(d));
}
__device__ __forceinline__ void ldsm4(uint32_t addr, uint32_t& a, uint32_t& b, uint32_t& c, uint32_t& d) {
    asm volatile("ldmatrix.sync.aligned.m8n8.x4.shared.b16 {%0,%1,%2,%3}, [%4];" : "=r"(a), "=r"(b), "=r"(c), "=r"(d) : "r"(addr));
}

template <int N> struct Wgmma;
template <> struct Wgmma<160> {
  template <int TB> static __device__ __forceinline__ void mma(float (&d)[80], uint32_t da, uint32_t db) {
    asm volatile("{\n.reg .b64 a, b;\nmov.b64 a, {%80, %82};\nmov.b64 b, {%81, %82};\n"
      "wgmma.mma_async.sync.aligned.m64n160k16.f32.bf16.bf16 {%0, %1, %2, %3, %4, %5, %6, %7, %8, %9, %10, %11, %12, %13, %14, %15, %16, %17, %18, %19, %20, %21, %22, %23, %24, %25, %26, %27, %28, %29, %30, %31, %32, %33, %34, %35, %36, %37, %38, %39, %40, %41, %42, %43, %44, %45, %46, %47, %48, %49, %50, %51, %52, %53, %54, %55, %56, %57, %58, %59, %60, %61, %62, %63, %64, %65, %66, %67, %68, %69, %70, %71, %72, %73, %74, %75, %76, %77, %78, %79}, a, b, 1, 1, 1, 0, %83;\n}\n"
      : "+f"(d[0]), "+f"(d[1]), "+f"(d[2]), "+f"(d[3]), "+f"(d[4]), "+f"(d[5]), "+f"(d[6]), "+f"(d[7]), "+f"(d[8]), "+f"(d[9]), "+f"(d[10]), "+f"(d[11]), "+f"(d[12]), "+f"(d[13]), "+f"(d[14]), "+f"(d[15]), "+f"(d[16]), "+f"(d[17]), "+f"(d[18]), "+f"(d[19]), "+f"(d[20]), "+f"(d[21]), "+f"(d[22]), "+f"(d[23]), "+f"(d[24]), "+f"(d[25]), "+f"(d[26]), "+f"(d[27]), "+f"(d[28]), "+f"(d[29]), "+f"(d[30]), "+f"(d[31]), "+f"(d[32]), "+f"(d[33]), "+f"(d[34]), "+f"(d[35]), "+f"(d[36]), "+f"(d[37]), "+f"(d[38]), "+f"(d[39]), "+f"(d[40]), "+f"(d[41]), "+f"(d[42]), "+f"(d[43]), "+f"(d[44]), "+f"(d[45]), "+f"(d[46]), "+f"(d[47]), "+f"(d[48]), "+f"(d[49]), "+f"(d[50]), "+f"(d[51]), "+f"(d[52]), "+f"(d[53]), "+f"(d[54]), "+f"(d[55]), "+f"(d[56]), "+f"(d[57]), "+f"(d[58]), "+f"(d[59]), "+f"(d[60]), "+f"(d[61]), "+f"(d[62]), "+f"(d[63]), "+f"(d[64]), "+f"(d[65]), "+f"(d[66]), "+f"(d[67]), "+f"(d[68]), "+f"(d[69]), "+f"(d[70]), "+f"(d[71]), "+f"(d[72]), "+f"(d[73]), "+f"(d[74]), "+f"(d[75]), "+f"(d[76]), "+f"(d[77]), "+f"(d[78]), "+f"(d[79])
      : "r"(da), "r"(db), "r"(0x40000040), "n"(TB));
  }
};
template <> struct Wgmma<176> {
  template <int TB> static __device__ __forceinline__ void mma(float (&d)[88], uint32_t da, uint32_t db) {
    asm volatile("{\n.reg .b64 a, b;\nmov.b64 a, {%88, %90};\nmov.b64 b, {%89, %90};\n"
      "wgmma.mma_async.sync.aligned.m64n176k16.f32.bf16.bf16 {%0, %1, %2, %3, %4, %5, %6, %7, %8, %9, %10, %11, %12, %13, %14, %15, %16, %17, %18, %19, %20, %21, %22, %23, %24, %25, %26, %27, %28, %29, %30, %31, %32, %33, %34, %35, %36, %37, %38, %39, %40, %41, %42, %43, %44, %45, %46, %47, %48, %49, %50, %51, %52, %53, %54, %55, %56, %57, %58, %59, %60, %61, %62, %63, %64, %65, %66, %67, %68, %69, %70, %71, %72, %73, %74, %75, %76, %77, %78, %79, %80, %81, %82, %83, %84, %85, %86, %87}, a, b, 1, 1, 1, 0, %91;\n}\n"
      : "+f"(d[0]), "+f"(d[1]), "+f"(d[2]), "+f"(d[3]), "+f"(d[4]), "+f"(d[5]), "+f"(d[6]), "+f"(d[7]), "+f"(d[8]), "+f"(d[9]), "+f"(d[10]), "+f"(d[11]), "+f"(d[12]), "+f"(d[13]), "+f"(d[14]), "+f"(d[15]), "+f"(d[16]), "+f"(d[17]), "+f"(d[18]), "+f"(d[19]), "+f"(d[20]), "+f"(d[21]), "+f"(d[22]), "+f"(d[23]), "+f"(d[24]), "+f"(d[25]), "+f"(d[26]), "+f"(d[27]), "+f"(d[28]), "+f"(d[29]), "+f"(d[30]), "+f"(d[31]), "+f"(d[32]), "+f"(d[33]), "+f"(d[34]), "+f"(d[35]), "+f"(d[36]), "+f"(d[37]), "+f"(d[38]), "+f"(d[39]), "+f"(d[40]), "+f"(d[41]), "+f"(d[42]), "+f"(d[43]), "+f"(d[44]), "+f"(d[45]), "+f"(d[46]), "+f"(d[47]), "+f"(d[48]), "+f"(d[49]), "+f"(d[50]), "+f"(d[51]), "+f"(d[52]), "+f"(d[53]), "+f"(d[54]), "+f"(d[55]), "+f"(d[56]), "+f"(d[57]), "+f"(d[58]), "+f"(d[59]), "+f"(d[60]), "+f"(d[61]), "+f"(d[62]), "+f"(d[63]), "+f"(d[64]), "+f"(d[65]), "+f"(d[66]), "+f"(d[67]), "+f"(d[68]), "+f"(d[69]), "+f"(d[70]), "+f"(d[71]), "+f"(d[72]), "+f"(d[73]), "+f"(d[74]), "+f"(d[75]), "+f"(d[76]), "+f"(d[77]), "+f"(d[78]), "+f"(d[79]), "+f"(d[80]), "+f"(d[81]), "+f"(d[82]), "+f"(d[83]), "+f"(d[84]), "+f"(d[85]), "+f"(d[86]), "+f"(d[87])
      : "r"(da), "r"(db), "r"(0x40000040), "n"(TB));
  }
};
template <> struct Wgmma<256> {
  template <int TB> static __device__ __forceinline__ void mma(float (&d)[128], uint32_t da, uint32_t db) {
    asm volatile("{\n.reg .b64 a, b;\nmov.b64 a, {%128, %130};\nmov.b64 b, {%129, %130};\n"
      "wgmma.mma_async.sync.aligned.m64n256k16.f32.bf16.bf16 {%0, %1, %2, %3, %4, %5, %6, %7, %8, %9, %10, %11, %12, %13, %14, %15, %16, %17, %18, %19, %20, %21, %22, %23, %24, %25, %26, %27, %28, %29, %30, %31, %32, %33, %34, %35, %36, %37, %38, %39, %40, %41, %42, %43, %44, %45, %46, %47, %48, %49, %50, %51, %52, %53, %54, %55, %56, %57, %58, %59, %60, %61, %62, %63, %64, %65, %66, %67, %68, %69, %70, %71, %72, %73, %74, %75, %76, %77, %78, %79, %80, %81, %82, %83, %84, %85, %86, %87, %88, %89, %90, %91, %92, %93, %94, %95, %96, %97, %98, %99, %100, %101, %102, %103, %104, %105, %106, %107, %108, %109, %110, %111, %112, %113, %114, %115, %116, %117, %118, %119, %120, %121, %122, %123, %124, %125, %126, %127}, a, b, 1, 1, 1, 0, %131;\n}\n"
      : "+f"(d[0]), "+f"(d[1]), "+f"(d[2]), "+f"(d[3]), "+f"(d[4]), "+f"(d[5]), "+f"(d[6]), "+f"(d[7]), "+f"(d[8]), "+f"(d[9]), "+f"(d[10]), "+f"(d[11]), "+f"(d[12]), "+f"(d[13]), "+f"(d[14]), "+f"(d[15]), "+f"(d[16]), "+f"(d[17]), "+f"(d[18]), "+f"(d[19]), "+f"(d[20]), "+f"(d[21]), "+f"(d[22]), "+f"(d[23]), "+f"(d[24]), "+f"(d[25]), "+f"(d[26]), "+f"(d[27]), "+f"(d[28]), "+f"(d[29]), "+f"(d[30]), "+f"(d[31]), "+f"(d[32]), "+f"(d[33]), "+f"(d[34]), "+f"(d[35]), "+f"(d[36]), "+f"(d[37]), "+f"(d[38]), "+f"(d[39]), "+f"(d[40]), "+f"(d[41]), "+f"(d[42]), "+f"(d[43]), "+f"(d[44]), "+f"(d[45]), "+f"(d[46]), "+f"(d[47]), "+f"(d[48]), "+f"(d[49]), "+f"(d[50]), "+f"(d[51]), "+f"(d[52]), "+f"(d[53]), "+f"(d[54]), "+f"(d[55]), "+f"(d[56]), "+f"(d[57]), "+f"(d[58]), "+f"(d[59]), "+f"(d[60]), "+f"(d[61]), "+f"(d[62]), "+f"(d[63]), "+f"(d[64]), "+f"(d[65]), "+f"(d[66]), "+f"(d[67]), "+f"(d[68]), "+f"(d[69]), "+f"(d[70]), "+f"(d[71]), "+f"(d[72]), "+f"(d[73]), "+f"(d[74]), "+f"(d[75]), "+f"(d[76]), "+f"(d[77]), "+f"(d[78]), "+f"(d[79]), "+f"(d[80]), "+f"(d[81]), "+f"(d[82]), "+f"(d[83]), "+f"(d[84]), "+f"(d[85]), "+f"(d[86]), "+f"(d[87]), "+f"(d[88]), "+f"(d[89]), "+f"(d[90]), "+f"(d[91]), "+f"(d[92]), "+f"(d[93]), "+f"(d[94]), "+f"(d[95]), "+f"(d[96]), "+f"(d[97]), "+f"(d[98]), "+f"(d[99]), "+f"(d[100]), "+f"(d[101]), "+f"(d[102]), "+f"(d[103]), "+f"(d[104]), "+f"(d[105]), "+f"(d[106]), "+f"(d[107]), "+f"(d[108]), "+f"(d[109]), "+f"(d[110]), "+f"(d[111]), "+f"(d[112]), "+f"(d[113]), "+f"(d[114]), "+f"(d[115]), "+f"(d[116]), "+f"(d[117]), "+f"(d[118]), "+f"(d[119]), "+f"(d[120]), "+f"(d[121]), "+f"(d[122]), "+f"(d[123]), "+f"(d[124]), "+f"(d[125]), "+f"(d[126]), "+f"(d[127])
      : "r"(da), "r"(db), "r"(0x40000040), "n"(TB));
  }
};


struct Cons {
    uint32_t ring, full, empty, full2;
    uint32_t rank;
    int wg, tid;
    __device__ __forceinline__ void wait_full(uint32_t c) const { mbar_wait(full + (c % NB) * 8, (c / NB) & 1); }
    __device__ __forceinline__ uint32_t wait_stage(uint32_t c) const {
        wait_full(c + wg);
        return ring + (c_sched.off[c + wg] & 0xFF) * 1024;
    }
    __device__ __forceinline__ void release(uint32_t c) const {
        if (tid < 2) mbar_arrive_cluster(empty + (c % NB) * 8, rank ^ tid);
    }
};

template <int N, bool A_IS_W, bool HALF_LAST, int TAIL, bool BT = false>
__device__ __forceinline__ void mainloop(float (&acc)[N / 2], const Cons& cx, uint32_t base, int nsteps, int m2 = -1) {
#pragma unroll
    for (int i = 0; i < N / 2; i++) acc[i] = 0.f;
    const uint32_t r4 = (cx.ring & 0x3FFFF) >> 4;
    const uint32_t dB = r4 | ((BT ? 512u : 1u) << 16), dA = (r4 | (1u << 16)) + cx.wg * 512;
    const int nfull = HALF_LAST ? nsteps - 1 : nsteps;
    uint32_t e = c_sched.off[base];
#pragma unroll 1
    for (int k = 0; k < nfull; k++) {
        const uint32_t c = base + k;
        const uint32_t da = dA + (A_IS_W ? e & 0xFF : e >> 16) * 64, db = dB + (A_IS_W ? e >> 16 : e & 0xFF) * 64;
        e = c_sched.off[c + 1];
        bool pending = k > 0;
        if (TAIL && cx.wg == 1 && k == nsteps - TAIL) { wg_wait<0>(); cx.release(c - 1); pending = false; bar_sync(4, 256); }
        const bool two = m2 >= 0 && cx.wg == 1;
        const uint32_t b2 = cx.full2 + ((m2 + k) & 7) * 8, p2 = ((m2 + k) >> 3) & 1;
        if (!__all_sync(0xffffffffu, mbar_test(cx.full + (c % NB) * 8, (c / NB) & 1) && (!two || mbar_test(b2, p2)))) {
            if (pending) { wg_wait<0>(); cx.release(c - 1); pending = false; }
            cx.wait_full(c);
            if (two) mbar_wait(b2, p2);
        }
        wg_fence();
#pragma unroll
        for (int kk = 0; kk < 4; kk++) Wgmma<N>::template mma<BT>(acc, da + kk * 2, db + kk * (BT ? 128 : 2));
        wg_commit();
        if (TAIL && k == nfull - 1 && cx.wg == 0) bar_arrive(4, 256);
        wg_wait<1>();
        if (pending) cx.release(c - 1);
    }
    if (HALF_LAST) {
        const uint32_t c = base + nfull;
        const uint32_t da = dA + (e >> 16) * 64 + cx.rank * 4, db = dB + (e & 0xFF) * 64 + cx.rank * 4;
        cx.wait_full(c);
        wg_fence();
#pragma unroll
        for (int kk = 0; kk < 2; kk++) Wgmma<N>::template mma<0>(acc, da + kk * 2, db + kk * 2);
        wg_commit();
        wg_wait<1>();
        cx.release(c - 1);
    }
    wg_wait<0>();
    cx.release(base + nsteps - 1);
}

__device__ __forceinline__ void wait_space(uint32_t empty, uint32_t c, uint32_t w) {
    if (w) {
        const uint32_t a = c - (w & 0xFF);
        mbar_wait(empty + (a % NB) * 8, (a / NB) & 1);
        if (w >> 8) {
            const uint32_t b = c - ((w >> 8) & 0xFF);
            mbar_wait(empty + (b % NB) * 8, (b / NB) & 1);
            if (w >> 16) {
                const uint32_t d = c - (w >> 16);
                mbar_wait(empty + (d % NB) * 8, (d / NB) & 1);
            }
        }
    }
}

__device__ __forceinline__ void stage_done(uint32_t stgbar) {
    fence_async_smem();
    __syncwarp();
    if ((threadIdx.x & 31) == 0) mbar_arrive(stgbar);
}

__device__ __forceinline__ void gather_stats(const uint4* rows, uint32_t tag, int lane, float2* out) {
    uint64_t a[2][8], b[2][8];
    unsigned n = 0;
    while (true) {
        bool ok = true;
#pragma unroll
        for (int h = 0; h < 2; h++)
#pragma unroll
            for (int i = 0; i < 8; i++)
                asm volatile("ld.relaxed.gpu.global.v2.u64 {%0,%1}, [%2];" : "=l"(a[h][i]), "=l"(b[h][i]) : "l"(rows + i * S_ + h * 32 + lane) : "memory");
#pragma unroll
        for (int h = 0; h < 2; h++)
#pragma unroll
            for (int i = 0; i < 8; i++) ok = ok && (uint32_t)(a[h][i] >> 32) == tag && (uint32_t)(b[h][i] >> 32) == tag;
        if (__all_sync(0xffffffffu, ok)) break;
        if (++n > SPIN_LIMIT) __trap();
        __nanosleep(300);
    }
#pragma unroll
    for (int h = 0; h < 2; h++) {
        float s = 0.f, m2 = 0.f;
#pragma unroll
        for (int i = 0; i < 8; i++) s += __uint_as_float((uint32_t)a[h][i]);
        const float mean = s * 0.125f;
#pragma unroll
        for (int i = 0; i < 8; i++) { const float d = __uint_as_float((uint32_t)a[h][i]) - mean; m2 += __uint_as_float((uint32_t)b[h][i]) + 80.f * d * d; }
        out[h * 32 + lane] = make_float2(-mean, rsqrtf(m2 * (1.f / D_) + LN_EPS));
    }
}

__device__ __forceinline__ unsigned ld_relaxed(const unsigned* p) {
    unsigned v; asm volatile("ld.relaxed.gpu.global.u32 %0, [%1];" : "=r"(v) : "l"(p) : "memory"); return v;
}
__device__ __forceinline__ void spin_cycles(unsigned n) { const unsigned t0 = clock(); while (clock() - t0 < n) {} }
__device__ __forceinline__ void wait_tags(const unsigned* line, unsigned tag, uint32_t need, uint32_t& ready, int lane) {
    if ((ready & need) == need) return;
    const unsigned* p = line + lane;
    unsigned v0 = ld_relaxed(p);
    spin_cycles(POLL_GAP);
    unsigned v1 = ld_relaxed(p);
    spin_cycles(POLL_GAP);
    unsigned v2 = ld_relaxed(p);
    unsigned n = 0;
    while (true) {
        ready = __ballot_sync(0xffffffffu, (int)(v0 - tag) >= 0);
        if ((ready & need) == need) break;
        v0 = ld_relaxed(p);
        ready = __ballot_sync(0xffffffffu, (int)(v1 - tag) >= 0);
        if ((ready & need) == need) break;
        v1 = ld_relaxed(p);
        ready = __ballot_sync(0xffffffffu, (int)(v2 - tag) >= 0);
        if ((ready & need) == need) break;
        v2 = ld_relaxed(p);
        if (++n > SPIN_LIMIT) __trap();
    }
    asm volatile("fence.acquire.gpu;" ::: "memory");
    __syncwarp();
    fence_async_all();
}
__device__ __forceinline__ void set_tag(unsigned* p, unsigned tag) { asm volatile("st.release.gpu.global.u32 [%0], %1;" ::"l"(p), "r"(tag) : "memory"); }

constexpr int HWARPS = 9, NHW = NHELP * HWARPS;
__device__ __forceinline__ bool repack_coords(int hw, int n, int& mat, int& kb, int& fb) {
    int t;
    if (n < 10) { mat = hw & 1; fb = hw < 22 ? F0 / 64 + (hw >> 1) : (hw - 22) >> 1; kb = n; return true; }
    if (n < 20) {
        if (hw < 18) { mat = hw & 1; fb = 7 + (hw >> 1); kb = n - 10; return true; }
        t = (hw - 18) * 10 + (n - 10);
    } else {
        t = 180 + hw + (n - 20) * NHW;
        if (t >= 270) return false;
    }
    mat = 2; kb = t % 10; fb = t / 10;
    return true;
}
__device__ __forceinline__ void repack_warp(const Maps& maps, int hw, uint32_t buf, uint32_t bar, int lane) {
    uint64_t stream_pol;
    asm volatile("createpolicy.fractional.L2::evict_first.b64 %0, 1.0;" : "=l"(stream_pol));
    auto load = [&](int n, int s) {
        int mat, kb, fb;
        if (lane == 0 && repack_coords(hw, n, mat, kb, fb)) {
            mbar_expect_tx(bar + s * 8, 8192);
            if (mat < 2 && fb < F0 / 64) tma_load(buf + s * 8192, &maps.Rs[mat], fb * 64, kb * 64, bar + s * 8);
            else if (mat < 2) tma_load_stream(buf + s * 8192, &maps.Rs[mat], fb * 64, kb * 64, bar + s * 8, stream_pol);
            else tma_load_stream(buf + s * 8192, &maps.Rs[2], kb * 64, fb * 64, bar + s * 8, stream_pol);
        }
    };
    load(0, 0);
    load(1, 1);
    int s = 0, ph = 0, mat, kb, fb;
    const int r8 = lane & 7, m = lane >> 3;
    float cs[8];
#pragma unroll
    for (int cb = 0; cb < 8; cb++) cs[cb] = 0.f;
#pragma unroll 1
    for (int n = 0; repack_coords(hw, n, mat, kb, fb); n++) {
        mbar_wait(bar + s * 8, ph);
        const uint32_t t = buf + s * 8192;
        uint32_t v[8][2][4];
#pragma unroll
        for (int cb = 0; cb < 8; cb++)
#pragma unroll
            for (int h = 0; h < 2; h++)
                asm volatile("ldmatrix.sync.aligned.m8n8.x4.trans.shared.b16 {%0,%1,%2,%3}, [%4];"
                             : "=r"(v[cb][h][0]), "=r"(v[cb][h][1]), "=r"(v[cb][h][2]), "=r"(v[cb][h][3])
                             : "r"(t + ((h * 4 + m) * 8 + r8) * 128 + ((cb ^ r8) * 16)));
        __syncwarp();
        const bool keep = mat == 2 || fb >= F0 / 64;
        if (keep) {
#pragma unroll
            for (int cb = 0; cb < 8; cb++)
#pragma unroll
                for (int h = 0; h < 2; h++)
                    stsm4(t + (cb * 8 + r8) * 128 + (((h * 4 + m) ^ r8) * 16), v[cb][h][0], v[cb][h][1], v[cb][h][2], v[cb][h][3]);
        }
        fence_async_smem();
        __syncwarp();
        if (lane == 0) {
            if (mat == 2) tma_store(&maps.Rd, fb * 64, kb * 64, t);
            else if (keep) tma_store(&maps.Rgu, kb * 64, mat * F_ + fb * 64, t);
            asm volatile("cp.async.bulk.commit_group;\ncp.async.bulk.wait_group.read 1;" ::: "memory");
        }
        load(n + 2, s == 0 ? 2 : s - 1);
#pragma unroll
        for (int cb = 0; cb < 8; cb++)
#pragma unroll
            for (int h = 0; h < 2; h++)
#pragma unroll
                for (int e = 0; e < 4; e++) cs[cb] += bf_lo(v[cb][h][e]) + bf_hi(v[cb][h][e]);
        if (n == 9 || n == 19) {
#pragma unroll
            for (int cb = 0; cb < 8; cb++) {
                float x = cs[cb];
                x += __shfl_xor_sync(0xffffffffu, x, 1);
                x += __shfl_xor_sync(0xffffffffu, x, 2);
                if (mat < 2 && (lane & 3) == 0) g_cs[mat * F_ + fb * 64 + cb * 8 + (lane >> 2)] = x;
                cs[cb] = 0.f;
            }
            __syncwarp();
            if (lane == 0 && mat < 2) { bulk_wait(); flag_add_release(CNT_W + keep, 1); }
        }
        if (++s == 3) { s = 0; ph ^= 1; }
    }
    if (lane == 0) { bulk_wait(); flag_add_release(CNT_W + 2, 1); }
}

template <int NP, bool SWZ, int I0, int I1>
__device__ __forceinline__ void gu_epilogue(float (&acc)[NP / 2], uint32_t stg, const float* cs, const float (&nm)[2], const float (&rs)[2],
                                            int w4, int lane) {
    constexpr int NI = I1 - I0;
    const int q = lane & 3;
    const int m = lane >> 3;
    const int row = w4 * 16 + (m & 1) * 8 + (lane & 7);
    const uint32_t addr = SWZ ? stg + row * 128 : stg + row * (NI * 16) + (m >> 1) * 16;
    uint32_t o[4];
#pragma unroll
    for (int i = I0; i < I1; i++) {
        const float2 cg = *(const float2*)(cs + 8 * i + 2 * q), cu = *(const float2*)(cs + NP / 2 + 8 * i + 2 * q);
#pragma unroll
        for (int h = 0; h < 2; h++) {
            const float tg0 = fmaf(nm[h], cg.x, acc[4 * i + 2 * h]), tg1 = fmaf(nm[h], cg.y, acc[4 * i + 2 * h + 1]);
            const float tu0 = fmaf(nm[h], cu.x, acc[NP / 4 + 4 * i + 2 * h]), tu1 = fmaf(nm[h], cu.y, acc[NP / 4 + 4 * i + 2 * h + 1]);
            const float h0 = (0.5f * rs[h]) * tg0, h1 = (0.5f * rs[h]) * tg1;
            float t0, t1;
            asm("tanh.approx.f32 %0, %1;" : "=f"(t0) : "f"(h0));
            asm("tanh.approx.f32 %0, %1;" : "=f"(t1) : "f"(h1));
            const float p0 = h0 * (tu0 * rs[h]), p1 = h1 * (tu1 * rs[h]);
            o[(i & 1) * 2 + h] = pack_bf16(fmaf(p0, t0, p0), fmaf(p1, t1, p1));
        }
        if (i & 1) {
            if (SWZ) stsm4(addr + ((i - 1) >> 3) * 8192 + (((((i - 1) & 7) + (m >> 1)) ^ (lane & 7)) * 16), o[0], o[1], o[2], o[3]);
            else stsm4(addr + (i - 1 - I0) * 16, o[0], o[1], o[2], o[3]);
        }
    }
    if (NI & 1) stsm2(addr - (m >> 1) * 16 + (NI - 1) * 16, o[0], o[1]);
}

__global__ void __cluster_dims__(2, 1, 1) __launch_bounds__(NTHREADS, 1)
fused_kernel(const __grid_constant__ Maps maps, const __nv_bfloat16* __restrict__ x0, const __nv_bfloat16* __restrict__ wg_,
             const __nv_bfloat16* __restrict__ wu_, const __nv_bfloat16* __restrict__ wd_, const __nv_bfloat16* __restrict__ wr_,
             const __nv_bfloat16* __restrict__ wi_) {
    extern __shared__ __align__(1024) uint8_t smem_raw[];
    const uint32_t ring = smem_u32(smem_raw);
    Ctl* ctl = (Ctl*)(smem_raw + RING);
    const int role = maps.role[blockIdx.x >> 1], g = role >> 2, pr = role & 3, rank = blockIdx.x & 1, i8 = pr * 2 + rank, cta = role * 2 + rank;
    const int warp = __shfl_sync(0xffffffffu, threadIdx.x >> 5, 0), lane = threadIdx.x & 31;
    const uint32_t full = smem_u32(ctl->full), empty = smem_u32(ctl->empty), stgb = smem_u32(ctl->stg), xchb = smem_u32(ctl->xch),
                   stab = smem_u32(ctl->sta), full2 = smem_u32(ctl->full2);

    if (role >= 64) {
        if (warp < HWARPS) {
            if (lane == 0) { for (int i = 0; i < 3; i++) mbar_init(full + warp * 24 + i * 8, 1); fence_async_smem(); }
            __syncwarp();
            repack_warp(maps, warp * NHELP + (role - 64) * 2 + rank, ring + warp * 24576, full + warp * 24, lane);
        }
        return;
    }
    if (threadIdx.x == 256) {
        if (ring & 1023) __trap();
        for (int s = 0; s < NB; s++) { mbar_init(full + s * 8, 2); mbar_init(empty + s * 8, 4); }
        mbar_init(stgb, 4); mbar_init(stgb + 8, 4); mbar_init(stgb + 16, 4); mbar_init(stgb + 24, 4); mbar_init(stab + 16, 1); mbar_init(xchb, 1); mbar_init(xchb + 8, 1);
        mbar_init(stab, 1); mbar_init(stab + 8, 1);
        for (int s = 0; s < 8; s++) mbar_init(full2 + s * 8, 1);
        asm volatile("fence.mbarrier_init.release.cluster;" ::: "memory");
    }
    __syncwarp();
    asm volatile("barrier.cluster.arrive.relaxed.aligned;" ::: "memory");
    if (warp == 9 && lane < (int)(offsetof(Maps, role) / sizeof(CUtensorMap)))
        asm volatile("prefetch.tensormap [%0];" ::"l"((const CUtensorMap*)&maps + lane) : "memory");
    __syncwarp();
    uint2 v[4][5];
    const int r0 = g * 128 + i8 * 16 + warp * 2;
    const int wrow0 = cta * 10 + warp, wrow1 = cta * 10 + 8 + (warp & 1);
    if (warp < 8) {
#pragma unroll
        for (int r = 0; r < 4; r++) {
            const int wr = r == 2 ? wrow0 : wrow1;
            const __nv_bfloat16* p = r < 2 ? x0 + (size_t)(r0 + r) * D_ : (wr < D_ ? wr_ + (size_t)wr * D_ : wi_ + (size_t)(wr - D_) * D_);
#pragma unroll
            for (int i = 0; i < 5; i++)
                asm volatile("ld.global.nc.v2.u32 {%0,%1}, [%2];" : "=r"(v[r][i].x), "=r"(v[r][i].y) : "l"((const uint2*)p + i * 32 + lane));
        }
    }
    unsigned epoch = 0;
    if (warp != 8 && warp != 10) asm volatile("ld.relaxed.gpu.global.u32 %0, [%1];" : "=r"(epoch) : "l"(&g_epoch) : "memory");
    asm volatile("barrier.cluster.wait.aligned;" ::: "memory");
    if (warp == 8 || warp == 10) asm volatile("ld.relaxed.gpu.global.u32 %0, [%1];" : "=r"(epoch) : "l"(&g_epoch) : "memory");

    if (warp >= 8) {
        if (warp == 8) {
            {
                uint32_t c = 0;
                const bool lead = lane == 0;
                uint64_t stream_pol;
                asm volatile("createpolicy.fractional.L2::evict_first.b64 %0, 1.0;" : "=l"(stream_pol));
                auto stg_stage = [&](uint32_t n = 2) {
                    wait_space(empty, c, c_sched.waitW[c]);
                    if (lead) asm volatile("mbarrier.arrive.shared::cta.b64 _, [%0], %1;" ::"r"(full + (c % NB) * 8), "r"(n) : "memory");
                    c++;
                };
#pragma unroll 1
                for (int L = 0; L < 2; L++) {
#pragma unroll 1
                    for (int k = 0; k < 10; k++, c++) {
                        const uint32_t e = c_sched.off[c], b = full + (c % NB) * 8;
                        wait_space(empty, c, c_sched.waitW[c]);
                        if (lead) {
                            mbar_arrive(b);
                            mbar_expect_tx(b, 20480 + 8192);
                            mbar_expect_tx(full2 + ((L * 30 + k) & 7) * 8, 8192);
                            tma_load(ring + (e & 0xFF) * 1024, &maps.Wh[i8 >> 2], k * 64, (i8 & 3) * 160, b);
                        }
                        if (lead && L == 0 && k >= 7) {
                            const __nv_bfloat16* p = k == 7 ? wg_ : k == 8 ? wu_ : wd_;
                            l2_prefetch(p + (size_t)cta * (D_ * F_ / NCTA), D_ * F_ / NCTA * 2);
                        }
                    }
                    stg_stage();
                    stg_stage();
#pragma unroll 1
                    for (int k = 0; k < 32; k++, c++) {
                        const uint32_t e = c_sched.off[c], b = full + (c % NB) * 8;
                        wait_space(empty, c, c_sched.waitW[c]);
                        if (lead) {
                            mbar_expect_tx(b, 16384);
                            tma_load_stream(ring + (e & 0xFF) * 1024, &maps.C[rank], KORD(k) * 64, g * 128, b, stream_pol);
                        }
                    }
                    stg_stage(1);
                    stg_stage(1);
#pragma unroll 1
                    for (int p = 0; p < 2; p++) {
                        if (L == 0 && p) flag_wait(CNT_W + 1, (epoch + 1) * 22);
                        const uint32_t wbytes = p ? NP1 * 128 : NP0 * 128;
                        const int wrow = NP0 / 2 * i8;
#pragma unroll 1
                        for (int k = 0; k < 10; k++, c++) {
                            const uint32_t e = c_sched.off[c], b = full + (c % NB) * 8;
                            wait_space(empty, c, c_sched.waitW[c]);
                            const uint32_t d = ring + (e & 0xFF) * 1024;
                            if (lead) {
                                mbar_arrive(b);
                                mbar_expect_tx(b, wbytes + 8192);
                                mbar_expect_tx(full2 + ((L * 30 + 10 + p * 10 + k) & 7) * 8, 8192);
                            }
                            if (!lead) {
                            } else if (p == 0) {
#pragma unroll
                                for (int j = 0; j < 4; j++) tma_load(d + j * 8192, &maps.Rs[j >> 1], wrow + (j & 1) * 64, k * 64, b);
                            } else {
#pragma unroll
                                for (int j = 0; j < 2; j++) {
                                    tma_load(d + j * (NP1 * 64), &maps.Wgu[0], k * 64, j * F_ + F0 + NA * i8, b);
                                    tma_load(d + j * (NP1 * 64) + NA * 128, &maps.Wgu[1], k * 64, j * F_ + F1 + NBC * i8, b);
                                }
                            }
                        }
                        stg_stage();
                        stg_stage();
                    }
                    if (L == 0) flag_wait(CNT_W + 2, (epoch + 1) * NHW);
#pragma unroll 1
                    for (int k = 0; k < 14; k++, c++) {
                        const uint32_t e = c_sched.off[c], b = full + (c % NB) * 8;
                        wait_space(empty, c, c_sched.waitW[c]);
                        if (lead) {
                            mbar_expect_tx(b, 20480);
                            tma_load(ring + (e & 0xFF) * 1024, &maps.Wd, k < 13 ? k * 128 + rank * 64 : 1664, pr * 160 + rank * 80, b);
                            tma_load(ring + (e & 0xFF) * 1024 + 10240, &maps.Wd, k < 13 ? k * 128 + rank * 64 : 1664, pr * 160 + 80 - rank * 80, b);
                        }
                    }
                    stg_stage(1);
                    stg_stage(1);
                }
            }
        } else if (warp == 10) {
            uint32_t c = 0;
            uint64_t stream_pol;
            asm volatile("createpolicy.fractional.L2::evict_first.b64 %0, 1.0;" : "=l"(stream_pol));
            auto load_res = [&](uint32_t d0, const CUtensorMap* m, int ro) {
#pragma unroll 1
                for (int w = 0; w < 2; w++) {
                    const uint32_t d = d0 + w, e = c_sched.off[d], b = full + (d % NB) * 8;
                    wait_space(empty, d, c_sched.waitX[d]);
                    if (lane == 0) {
                        mbar_expect_tx(b, 10240);
                        tma_load(ring + (e & 0xFF) * 1024, m, pr * 160 + rank * 80, ro + g * 128 + w * 64, b);
                    }
                }
            };
            auto issue = [&](uint32_t d, const CUtensorMap* m, int c0, int c1, int m2) {
                const uint32_t e = c_sched.off[d], b = full + (d % NB) * 8;
                wait_space(empty, d, c_sched.waitX[d]);
                if (lane == 0) {
                    if (m2 >= 0) {
                        tma_load_mc(ring + (e >> 16) * 1024 + rank * 8192, m, c0, c1, rank ? full2 + (m2 & 7) * 8 : b);
                    } else {
                        mbar_expect_tx(b, 16384);
                        tma_load_stream(ring + (e >> 16) * 1024, m, c0, c1, b, stream_pol);
                    }
                }
            };
            auto xmask = [&](int k, int w) -> uint32_t { return ((1u << (2 * ((64 * k) / 80))) | (1u << (2 * ((64 * k + 63) / 80)))) << w; };
#pragma unroll 1
            for (int L = 0; L < 2; L++) {
                const unsigned tagL = epoch * 2 + L + 1;
                uint32_t ready = L ? 0u : ~0u;
#pragma unroll 1
                for (int k = 0; k < 10; k++, c++) {
                    wait_tags(g_flagG[3][g], tagL - 1, xmask(k, rank), ready, lane);
                    issue(c, &maps.Xl[L], k * 64, g * 128 + rank * 64, L * 30 + k);
                }
                c += 2;
                ready = 0;
#pragma unroll 1
                for (int kk = 0; kk < 32; kk++, c++) {
                    const int k = KORD(kk);
                    wait_tags(g_flagAB[rank * 4 + pr], tagL, 1u << k, ready, lane);
                    const uint32_t e = c_sched.off[c], b = full + (c % NB) * 8;
                    wait_space(empty, c, c_sched.waitX[c]);
                    if (lane == 0) {
                        mbar_expect_tx(b, 20480);
                        tma_load_stream(ring + (e >> 16) * 1024, &maps.ABl[L], k * 64, rank * 720 + pr * 160, b, stream_pol);
                        tma_load_stream(ring + (e >> 16) * 1024 + 10240, &maps.ABl[L], k * 64, rank * 560 + pr * 160 + 80, b, stream_pol);
                    }
                }
                if (L) { ready = 0; wait_tags(g_flagG[3][g], tagL - 1, 3u << (2 * i8), ready, lane); }
                load_res(c, L ? &maps.Xo[0] : &maps.X0r, 0);
                c += 2;
                ready = 0;
#pragma unroll 1
                for (int p = 0; p < 2; p++) {
#pragma unroll 1
                    for (int k = 0; k < 10; k++, c++) {
                        wait_tags(g_flagG[0][g], tagL, xmask(k, rank), ready, lane);
                        issue(c, &maps.X1l, k * 64, L * S_ + g * 128 + rank * 64, L * 30 + 10 + p * 10 + k);
                    }
                    c += 2;
                }
                wait_tags(g_flagG[0][g], tagL, 3u << (2 * i8), ready, lane);
                ready = 0;
#pragma unroll 1
                for (int k = 0; k < 14; k++, c++) {
                    const int col = k < 13 ? k * 128 + rank * 64 : 1664;
                    if (k == F0 / 128 || k == F1 / 128) ready = 0;
                    if (col < F0) wait_tags(g_flagG[1][g], tagL, 3u << (2 * (col / (NP0 / 2))), ready, lane);
                    else if (col < F1) wait_tags(g_flagG[2][g], tagL, (3u << (2 * ((col - F0) / NA))) | (3u << (2 * ((col - F0 + 63) / NA))), ready, lane);
                    else wait_tags(g_flagG[4][g], tagL, (3u << (2 * ((col - F1) / NBC))) | (3u << (2 * ((col - F1 + 32) / NBC))) | (3u << (2 * ((col - F1 + 63) / NBC))), ready, lane);
                    issue(c, &maps.Al, col, g * 128, -1);
                }
                load_res(c, &maps.X1s, L * S_);
                c += 2;
            }
        } else {
            const int w = warp == 11;
            const uint32_t sb = stgb + w * 8;
            const int row0 = g * 128 + w * 64, col0 = pr * 160 + rank * 80;
            uint32_t c = 0, ph = 0;
            auto saddr = [&](uint32_t cc) -> uint32_t { return ring + (c_sched.off[cc] & 0xFF) * 1024; };
            auto release = [&](uint32_t cc) {
                mbar_arrive_cluster(empty + (cc % NB) * 8, rank); mbar_arrive_cluster(empty + (cc % NB) * 8, rank ^ 1);
            };
            auto publish_stats = [&](int idx, uint32_t first) {
                mbar_wait(full + (first % NB) * 8, (first / NB) & 1);
                gather_stats(&g_stat[idx][0][row0], epoch + 1, lane, ctl->rowstat + w * 64);
                __syncwarp();
                if (lane == 0) mbar_arrive(stab + w * 8);
            };
            auto finish = [&](uint32_t cc, unsigned* flag, unsigned tag) {
                bulk_commit_wait_read();
                release(cc);
                release(cc);
                bulk_wait();
                if (flag) set_tag(flag, tag);
            };
            {
                uint64_t v[3]; unsigned n = 0;
                while (true) {
                    bool ok = true;
#pragma unroll
                    for (int r = 0; r < 3; r++) {
                        const int i = min(lane + 32 * r, 79);
                        asm volatile("ld.relaxed.gpu.global.u64 %0, [%1];" : "=l"(v[r]) : "l"(&g_csh[i8 * 160 + w * 80 + i]) : "memory");
                    }
#pragma unroll
                    for (int r = 0; r < 3; r++) ok = ok && (uint32_t)(v[r] >> 32) == epoch + 1;
                    if (__all_sync(0xffffffffu, ok)) break;
                    if (++n > SPIN_LIMIT) __trap();
                    __nanosleep(300);
                }
#pragma unroll
                for (int r = 0; r < 3; r++) ctl->csh[w * 80 + min(lane + 32 * r, 79)] = __uint_as_float((uint32_t)v[r]);
            }
#pragma unroll 1
            for (int L = 0; L < 2; L++) {
                const unsigned tagL = epoch * 2 + L + 1;
                publish_stats(2 * L, c + 6);
                mbar_wait(sb, ph);
                if (w) mbar_wait(stab + 16, 0);
                if (lane == 0) {
                    tma_store(&maps.AB[L], row0, i8 * 160, ring + (c_sched.off[c + 10 + w] & 0xFF) * 1024);
                    finish(c + 10 + w, &g_flagAB[i8][g * 2 + w], tagL);
                    if (w == 0) mbar_arrive(stab + 16);
                }
                __syncwarp();
                mbar_wait(sb, ph ^ 1);
                if (w) mbar_wait(stab + 16, 1);
                if (lane == 0) {
                    tma_store(&maps.X1s, col0, L * S_ + row0, saddr(c + O_GU - 2 + w));
                    finish(c + O_GU - 2 + w, &g_flagG[0][g][i8 * 2 + w], tagL);
                    if (w == 0) mbar_arrive(stab + 16);
                }
                __syncwarp();
                mbar_wait(full + ((c + O_GU + 4) % NB) * 8, ((c + O_GU + 4) / NB) & 1);
                gather_stats(&g_stat[1 + 2 * L][0][row0], epoch + 1, lane, ctl->rowstat + w * 64);
                if (L == 0) {
                    flag_wait(CNT_W + (lane & 1), (epoch + 1) * ((lane & 1) ? 22 : 32));
                    __syncwarp();
                    float v[7];
#pragma unroll
                    for (int r = 0; r < 7; r++) {
                        const int i = min(lane + 32 * r, 215);
                        v[r] = __ldcg(&g_cs[w * F_ + (i < NP0 / 2 ? NP0 / 2 * i8 + i : i < NP0 / 2 + NA ? F0 + NA * i8 + (i - NP0 / 2) : F1 + NBC * i8 + (i - NP0 / 2 - NA))]);
                    }
#pragma unroll
                    for (int r = 0; r < 7; r++) {
                        const int i = min(lane + 32 * r, 215);
                        ctl->cs[i < NP0 / 2 ? w * (NP0 / 2) + i : NP0 + w * (NP1 / 2) + (i - NP0 / 2)] = v[r];
                    }
                }
                __syncwarp();
                if (lane == 0) mbar_arrive(stab + w * 8);
                uint32_t d = c + O_GU - 2 + w, p2 = ph;
                d += 12;
                mbar_wait(sb, p2); p2 ^= 1;
                if (lane == 0) {
                    tma_store(&maps.As[0], NP0 / 2 * i8, row0, saddr(d));
                    tma_store(&maps.As[0], NP0 / 2 * i8 + 64, row0, saddr(d) + 8192);
                    finish(d, &g_flagG[1][g][i8 * 2 + w], tagL);
                }
                __syncwarp();
                d += 12;
                mbar_wait(sb, p2); p2 ^= 1;
                if (lane == 0) {
                    tma_store(&maps.As[1], F0 + NA * i8, row0, saddr(d));
                    asm volatile("cp.async.bulk.commit_group;" ::: "memory");
                    bulk_wait();
                    set_tag(&g_flagG[2][g][i8 * 2 + w], tagL);
                }
                __syncwarp();
                mbar_wait(sb + 16, L);
                if (lane == 0) {
                    tma_store(&maps.As[2], F1 + NBC * i8, row0, saddr(d) + NA * 128);
                    finish(d, &g_flagG[4][g][i8 * 2 + w], tagL);
                }
                __syncwarp();
                d += 16;
                mbar_wait(sb, p2);
                if (lane == 0) {
                    tma_store(&maps.Xo[L], col0, row0, saddr(d));
                    finish(d, L ? nullptr : &g_flagG[3][g][i8 * 2 + w], tagL);
                }
                ph ^= 1;
                __syncwarp();
                c += LSTAGE;
            }
            if (cta == 0 && w == 0 && lane == 0) asm volatile("st.relaxed.gpu.global.u32 [%0], %1;" ::"l"(&g_epoch), "r"(epoch + 1) : "memory");
        }
        __syncwarp();
        asm volatile("barrier.cluster.arrive.relaxed.aligned;\nbarrier.cluster.wait.aligned;" ::: "memory");
        return;
    } else {
        Cons cx;
        cx.ring = ring; cx.full = full; cx.empty = empty; cx.full2 = full2; cx.rank = rank;
        cx.wg = warp >> 2; cx.tid = threadIdx.x & 127;
        const int wg = cx.wg, w4 = warp & 3, q = lane & 3;
        const uint32_t mystg = stgb + wg * 8;
        const uint64_t tag = (uint64_t)(epoch + 1) << 32;
        {
#pragma unroll
            for (int r = 0; r < 4; r++) {
                float s = 0.f;
#pragma unroll
                for (int i = 0; i < 5; i++) s += (bf_lo(v[r][i].x) + bf_hi(v[r][i].x)) + (bf_lo(v[r][i].y) + bf_hi(v[r][i].y));
#pragma unroll
                for (int o = 16; o; o >>= 1) s += __shfl_xor_sync(0xffffffffu, s, o);
                if (r < 2) {
                    const float mean = s * (1.f / D_);
                    float m2 = 0.f;
#pragma unroll
                    for (int i = 0; i < 5; i++) {
                        const float d0 = bf_lo(v[r][i].x) - mean, d1 = bf_hi(v[r][i].x) - mean, d2 = bf_lo(v[r][i].y) - mean, d3 = bf_hi(v[r][i].y) - mean;
                        m2 += (d0 * d0 + d1 * d1) + (d2 * d2 + d3 * d3);
                    }
#pragma unroll
                    for (int o = 16; o; o >>= 1) m2 += __shfl_xor_sync(0xffffffffu, m2, o);
                    if (lane < 8)
                        asm volatile("st.relaxed.gpu.global.v2.u64 [%0], {%1,%2};" ::"l"(&g_stat[0][lane][r0 + r]), "l"(tag | __float_as_uint(mean)),
                                     "l"(tag | __float_as_uint(m2 * 0.125f)) : "memory");
                } else if (lane == 0 && (r == 2 || warp < 2)) {
                    asm volatile("st.relaxed.gpu.global.u64 [%0], %1;" ::"l"(&g_csh[r == 2 ? wrow0 : wrow1]), "l"(tag | __float_as_uint(s)) : "memory");
                }
            }
        }
        uint32_t base = 0, xph = 0, sph = 0;
        const int erow = g * 128 + wg * 64 + w4 * 16 + (lane >> 2);
#pragma unroll 1
        for (int L = 0; L < 2; L++) {
#pragma unroll 1
            for (int ph = 0; ph < 2; ph++) {
                float nm[2], rs[2];
                auto load_stats = [&]() {
                    mbar_wait(stab + wg * 8, sph);
                    if (L == 0) mbar_wait(stab + (wg ^ 1) * 8, sph);
                    sph ^= 1;
                    const float2 s0 = ctl->rowstat[erow & 127], s1 = ctl->rowstat[(erow & 127) + 8];
                    nm[0] = s0.x; rs[0] = s0.y; nm[1] = s1.x; rs[1] = s1.y;
                };
                if (ph == 0) {
                    float acc[80];
                    mainloop<160, false, false, TAIL_G1>(acc, cx, base, 10, L * 30);
                    load_stats();
                    cx.wait_full(base + 10 + wg);
                    const uint32_t s = ring + (c_sched.off[base + 10 + wg] & 0xFF) * 1024;
                    base += O_TM;
                    if (i8 >= 4) { rs[0] = -rs[0]; rs[1] = -rs[1]; }
                    const float b0 = nm[0] * rs[0], b1 = nm[1] * rs[1];
                    const int m = lane >> 3;
                    const int chunk = w4 * 2 + (m & 1);
#pragma unroll
                    for (int j = 0; j < 20; j += 2) {
                        uint32_t r4[4];
#pragma unroll
                        for (int e = 0; e < 2; e++) {
                            const float2 c2 = *(const float2*)(ctl->csh + 8 * (j + e) + 2 * q);
                            r4[2 * e] = pack_bf16(fmaf(rs[0], acc[4 * (j + e)], b0 * c2.x), fmaf(rs[0], acc[4 * (j + e) + 1], b0 * c2.y));
                            r4[2 * e + 1] = pack_bf16(fmaf(rs[1], acc[4 * (j + e) + 2], b1 * c2.x), fmaf(rs[1], acc[4 * (j + e) + 3], b1 * c2.y));
                        }
                        const int feat = (j + (m >> 1)) * 8 + (lane & 7);
                        stsm4t(s + feat * 128 + ((chunk ^ (feat & 7)) * 16), r4[0], r4[1], r4[2], r4[3]);
                    }
                    stage_done(mystg);
                } else {
                    {
                        float acc[NP0 / 2];
                        mainloop<NP0, false, false, TAIL_GU, true>(acc, cx, base, 10, L * 30 + 10);
                        load_stats();
                        const uint32_t s = cx.wait_stage(base + 10);
                        base += 12;
                        gu_epilogue<NP0, true, 0, NP0 / 16>(acc, s, ctl->cs, nm, rs, w4, lane);
                        stage_done(mystg);
                    }
                    {
                        float acc[NP1 / 2];
                        mainloop<NP1, false, false, TAIL_GU1>(acc, cx, base, 10, L * 30 + 20);
                        const uint32_t s = cx.wait_stage(base + 10);
                        base += 12;
                        gu_epilogue<NP1, false, 0, NA / 8>(acc, s, ctl->cs + NP0, nm, rs, w4, lane);
                        stage_done(mystg);
                        gu_epilogue<NP1, false, NA / 8, NP1 / 16>(acc, s + NA * 128, ctl->cs + NP0, nm, rs, w4, lane);
                        stage_done(mystg + 16);
                    }
                }
                float acc[80];
                uint32_t nch;
                if (ph == 0) {
                    mainloop<160, true, false, TAIL_TM>(acc, cx, base, 32); nch = 32;
                } else { mainloop<160, false, true, TAIL_DN>(acc, cx, base, 14); nch = 14; }
                const uint32_t s = cx.wait_stage(base + nch);
                base += nch + 2;
                {
                    if (cx.tid == 0) mbar_expect_tx(xchb + wg * 8, 10240);
                    const uint32_t rb = mapa(xchb + wg * 8, rank ^ 1), ra = mapa(s + 10240 + cx.tid * 16, rank ^ 1);
#pragma unroll
                    for (int j = 0; j < 5; j++)
                        st_async4(ra + j * 2048, rb, pack_bf16(acc[40 + 8 * j], acc[41 + 8 * j]), pack_bf16(acc[42 + 8 * j], acc[43 + 8 * j]),
                                  pack_bf16(acc[44 + 8 * j], acc[45 + 8 * j]), pack_bf16(acc[46 + 8 * j], acc[47 + 8 * j]));
                }
                uint32_t res[20];
                const uint32_t saddr = s + (w4 * 16 + ((lane >> 3) & 1) * 8 + (lane & 7)) * 160 + (lane >> 4) * 16;
#pragma unroll
                for (int j = 0; j < 10; j += 2) ldsm4(saddr + j * 16, res[2 * j], res[2 * j + 1], res[2 * j + 2], res[2 * j + 3]);
#pragma unroll
                for (int j = 0; j < 20; j++) { acc[2 * j] += bf_lo(res[j]); acc[2 * j + 1] += bf_hi(res[j]); }
                mbar_wait_cluster(xchb + wg * 8, xph);
                xph ^= 1;
#pragma unroll
                for (int j = 0; j < 5; j++) {
                    uint32_t o[4];
                    asm volatile("ld.shared.v4.u32 {%0,%1,%2,%3}, [%4];" : "=r"(o[0]), "=r"(o[1]), "=r"(o[2]), "=r"(o[3]) : "r"(s + 10240 + j * 2048 + cx.tid * 16) : "memory");
#pragma unroll
                    for (int e = 0; e < 4; e++) res[4 * j + e] = pack_bf16(acc[8 * j + 2 * e] + bf_lo(o[e]), acc[8 * j + 2 * e + 1] + bf_hi(o[e]));
                    stsm4(saddr + j * 32, res[4 * j], res[4 * j + 1], res[4 * j + 2], res[4 * j + 3]);
                }
                stage_done(mystg);
                if (!(ph == 1 && L == 1)) {
                    float st_mean = 0.f, st_m2 = 0.f;
#pragma unroll
                    for (int h = 0; h < 2; h++) {
                        float t = 0.f;
#pragma unroll
                        for (int j = 0; j < 10; j++) t += bf_lo(res[2 * j + h]) + bf_hi(res[2 * j + h]);
                        t += __shfl_xor_sync(0xffffffffu, t, 1);
                        t += __shfl_xor_sync(0xffffffffu, t, 2);
                        const float mean = t * (1.f / 80.f);
                        float m2 = 0.f;
#pragma unroll
                        for (int j = 0; j < 10; j++) {
                            const float d0 = bf_lo(res[2 * j + h]) - mean, d1 = bf_hi(res[2 * j + h]) - mean;
                            m2 = fmaf(d0, d0, m2); m2 = fmaf(d1, d1, m2);
                        }
                        m2 += __shfl_xor_sync(0xffffffffu, m2, 1);
                        m2 += __shfl_xor_sync(0xffffffffu, m2, 2);
                        if (q == h) { st_mean = mean; st_m2 = m2; }
                    }
                    cx.wait_full(base);
                    if (q < 2)
                        asm volatile("st.relaxed.gpu.global.v2.u64 [%0], {%1,%2};" ::"l"(&g_stat[1 + 2 * L + ph][i8][erow + 8 * q]),
                                     "l"(tag | __float_as_uint(st_mean)), "l"(tag | __float_as_uint(st_m2)) : "memory");
                }
            }
        }
        __syncwarp();
        asm volatile("barrier.cluster.arrive.relaxed.aligned;\nbarrier.cluster.wait.aligned;" ::: "memory");
    }
}

typedef CUresult (*EncodeFn)(CUtensorMap*, CUtensorMapDataType, cuuint32_t, void*, const cuuint64_t*, const cuuint64_t*, const cuuint32_t*,
                             const cuuint32_t*, CUtensorMapInterleave, CUtensorMapSwizzle, CUtensorMapL2promotion, CUtensorMapFloatOOBfill);

void make_map(EncodeFn enc, CUtensorMap* m, const void* p, int rows, int cols, int box_cols, int box_rows, bool swz) {
    cuuint64_t gd[2] = {(cuuint64_t)cols, (cuuint64_t)rows};
    cuuint64_t gs[1] = {(cuuint64_t)cols * 2};
    cuuint32_t bd[2] = {(cuuint32_t)box_cols, (cuuint32_t)box_rows};
    cuuint32_t es[2] = {1, 1};
    enc(m, CU_TENSOR_MAP_DATA_TYPE_BFLOAT16, 2, const_cast<void*>(p), gd, gs, bd, es, CU_TENSOR_MAP_INTERLEAVE_NONE,
        swz ? CU_TENSOR_MAP_SWIZZLE_128B : CU_TENSOR_MAP_SWIZZLE_NONE, CU_TENSOR_MAP_L2_PROMOTION_L2_128B, CU_TENSOR_MAP_FLOAT_OOB_FILL_NONE);
}

__global__ void probe_kernel() {}

int assign_roles(uint8_t* role) {
    int n[9] = {0};
    cudaFuncSetAttribute(probe_kernel, cudaFuncAttributeMaxDynamicSharedMemorySize, 200 * 1024);
    cudaFuncSetAttribute(probe_kernel, cudaFuncAttributeNonPortableClusterSizeAllowed, 1);
    for (int k = 1; k <= 8; k++) {
        cudaLaunchConfig_t cfg = {};
        cfg.gridDim = dim3(2 * k * 16); cfg.blockDim = dim3(NTHREADS); cfg.dynamicSmemBytes = 200 * 1024;
        cudaLaunchAttribute at[1];
        at[0].id = cudaLaunchAttributeClusterDimension;
        at[0].val.clusterDim.x = 2 * k; at[0].val.clusterDim.y = 1; at[0].val.clusterDim.z = 1;
        cfg.attrs = at; cfg.numAttrs = 1;
        if (cudaOccupancyMaxActiveClusters(&n[k], probe_kernel, &cfg) != cudaSuccess) { n[k] = 0; (void)cudaGetLastError(); }
    }
    int c[11] = {0};
    c[8] = n[8]; c[7] = n[7]; c[6] = n[6]; c[5] = n[5]; c[4] = n[4] - c[8]; c[2] = n[2] - c[4] - c[6] - c[8];
    c[3] = c[4]; c[9] = n[3] - c[3] - c[6];
    if (c[9] > c[8]) { c[3] += c[9] - c[8]; c[9] = c[8]; }
    c[1] = n[1]; for (int s = 2; s <= 9; s++) c[1] -= c[s];
    bool ok = c[9] >= 0;
    for (int s = 1; s < 9; s++) ok = ok && c[s] >= c[s + 1];
    int grp[66];
    for (int i = 0; i < 66; i++) grp[i] = -1;
    int ng = 0;
    if (ok) {
        int start[10], pos = c[1] - c[2];
        for (int r = 0; r < 9; r++) { start[r] = pos; pos += c[r == 0 ? 2 : r + 1]; }
        for (int b = 0; b < 2; b++)
            for (int i = 0; i < c[4 * b + 4] && ng < 16; i++) {
                if (start[4 * b + 3] + i >= 66) break;
                for (int p = 0; p < 4; p++) grp[start[4 * b + p] + i] = ng * 4 + p;
                ng++;
            }
    }
    int next = ng * 4;
    for (int i = 0; i < 66; i++) role[i] = (uint8_t)(grp[i] >= 0 ? grp[i] : next++);
    return n[1];
}

template <typename T> void* sym_addr(T& sym) { void* p = nullptr; cudaGetSymbolAddress(&p, sym); return p; }

}

extern "C" void kernel_launch(void* const* d_in, const int* in_sizes, int n_in, void* d_out, int out_size) {
    (void)in_sizes; (void)n_in; (void)out_size;
    void* fn = nullptr;
    cudaDriverEntryPointQueryResult qr;
    cudaGetDriverEntryPoint("cuTensorMapEncodeTiled", &fn, cudaEnableDefault, &qr);
    EncodeFn enc = (EncodeFn)fn;
    Maps mp;
    __nv_bfloat16* abT = (__nv_bfloat16*)sym_addr(g_abT);
    void *x1 = sym_addr(g_x1), *x2 = sym_addr(g_x2), *act = sym_addr(g_act), *wgu = sym_addr(g_wguT), *wdT = sym_addr(g_wdT);
    make_map(enc, &mp.C[0], d_in[1], S_, S_, 64, 128, true);
    make_map(enc, &mp.C[1], d_in[2], S_, S_, 64, 128, true);
    make_map(enc, &mp.AB[0], abT, 2 * D_, S_, 64, 160, true);
    make_map(enc, &mp.AB[1], abT + 2 * D_ * S_, 2 * D_, S_, 64, 160, true);
    make_map(enc, &mp.ABl[0], abT, 2 * D_, S_, 64, 80, true);
    make_map(enc, &mp.ABl[1], abT + 2 * D_ * S_, 2 * D_, S_, 64, 80, true);
    make_map(enc, &mp.Wh[0], d_in[3], D_, D_, 64, 160, true);
    make_map(enc, &mp.Wh[1], d_in[4], D_, D_, 64, 160, true);
    make_map(enc, &mp.Xl[0], d_in[0], S_, D_, 64, 64, true);
    make_map(enc, &mp.Xl[1], x2, S_, D_, 64, 64, true);
    make_map(enc, &mp.X1l, x1, 2 * S_, D_, 64, 64, true);
    make_map(enc, &mp.X1s, x1, 2 * S_, D_, 80, 64, false);
    make_map(enc, &mp.Xo[0], x2, S_, D_, 80, 64, false);
    make_map(enc, &mp.Xo[1], d_out, S_, D_, 80, 64, false);
    make_map(enc, &mp.X0r, d_in[0], S_, D_, 80, 64, false);
    make_map(enc, &mp.Wgu[0], wgu, 2 * F_, D_, 64, NA, true);
    make_map(enc, &mp.Wgu[1], wgu, 2 * F_, D_, 64, NBC, true);
    make_map(enc, &mp.Al, act, S_, F_, 64, 128, true);
    make_map(enc, &mp.As[0], act, S_, F_, 64, 64, true);
    make_map(enc, &mp.As[1], act, S_, F_, NA, 64, false);
    make_map(enc, &mp.As[2], act, S_, F_, NBC, 64, false);
    make_map(enc, &mp.Wd, wdT, D_, F_, 64, 80, true);
    make_map(enc, &mp.Rs[0], d_in[6], D_, F_, 64, 64, true);
    make_map(enc, &mp.Rs[1], d_in[7], D_, F_, 64, 64, true);
    make_map(enc, &mp.Rs[2], d_in[8], F_, D_, 64, 64, true);
    make_map(enc, &mp.Rd, wdT, D_, F_, 64, 64, true);
    make_map(enc, &mp.Rgu, wgu, 2 * F_, D_, 64, 64, true);
    const int nclusters = assign_roles(mp.role);
    const int smem = RING + sizeof(Ctl);
    cudaFuncSetAttribute(fused_kernel, cudaFuncAttributeMaxDynamicSharedMemorySize, smem);
    auto launch = [&](int ctas) {
        fused_kernel<<<ctas, NTHREADS, smem>>>(mp, (const __nv_bfloat16*)d_in[0], (const __nv_bfloat16*)d_in[6], (const __nv_bfloat16*)d_in[7],
                                               (const __nv_bfloat16*)d_in[8], (const __nv_bfloat16*)d_in[3], (const __nv_bfloat16*)d_in[4]);
    };
    if (nclusters >= (NCTA + NHELP) / 2) launch(NCTA + NHELP);
    else {
        mp.role[0] = 64; mp.role[1] = 65;
        launch(NHELP);
        for (int i = 0; i < 64; i++) mp.role[i] = (uint8_t)i;
        launch(NCTA);
    }
}
```
